```python
import torch

def _softmax(x, axis=-1):
    return torch.softmax(x, dim=axis)
def _gelu(x):
    return torch.nn.functional.gelu(x, approximate="tanh")
def _silu(x):
    return torch.nn.functional.silu(x)
def _sigmoid(x):
    return torch.sigmoid(x)
def _layernorm(x, axis=-1, eps=1e-5):
    m = x.mean(dim=axis, keepdim=True)
    v = x.var(dim=axis, keepdim=True, unbiased=False)
    return (x - m) / torch.sqrt(v + eps)
def _scatter_add(tgt, idx, src, axis=0):
    return tgt.clone().index_add_(axis, idx, src)
def _segment_sum(src, seg, n):
    out = torch.zeros((n,) + src.shape[1:], dtype=src.dtype)
    return out.index_add_(0, seg, src)
def _pad(x, pw):
    flat = tuple(v for pair in reversed(pw) for v in pair)
    return torch.nn.functional.pad(x, flat)

kernel_name = 'standalone__dense_activation_squared_relu__prompt'

def setup_inputs():

    _w = (lambda a: (lambda t: t.to(torch.bfloat16) if t.is_floating_point() else t)(torch.as_tensor(a)))
    B, S, D, F = 1, 2048, 640, 1536
    return {
        "x": _w((lambda *s: torch.randn(*s, dtype=torch.bfloat16) * 0.05)(B, S, D)),
        "w1": _w((lambda *s: torch.randn(*s, dtype=torch.bfloat16) * 0.05)(D, F)),
        "b1": _w((lambda *s: torch.randn(*s, dtype=torch.bfloat16) * 0.05)(F)),
        "w2": _w((lambda *s: torch.randn(*s, dtype=torch.bfloat16) * 0.05)(F, D)),
        "b2": _w((lambda *s: torch.randn(*s, dtype=torch.bfloat16) * 0.05)(D)),
    }

def reference(x, w1, b1, w2, b2):
    h = torch.einsum("bsd,df->bsf", x, w1) + b1
    zero = torch.zeros_like(h)
    r = torch.where(h > zero, h, zero)
    h = r * r
    out = torch.einsum("bsf,fd->bsd", h, w2) + b2
    return out
```

```cpp
#include <cuda_runtime.h>
#include <cuda_bf16.h>
#include <cuda.h>
#include <stdint.h>

namespace {

constexpr int SEQ = 2048, DM = 640, FF = 1536;
constexpr int NTHREADS = 448, NCTAS = 132;

constexpr int TILE = 8192;
constexpr int W_ARR = 5 * TILE;
constexpr int W2_SLOTS = 8;
constexpr int OFF_X = 0;
constexpr int OFF_W = 10 * TILE;
constexpr int OFF_REM = OFF_W + 2 * W_ARR;
constexpr int OFF_SA = OFF_REM + 24 * 2048;
constexpr int OFF_BAR = OFF_SA + 2 * TILE;
constexpr int OFF_BIAS = OFF_BAR + 1024;
constexpr int SMEM_BYTES = OFF_BIAS + 1024;
static_assert(SMEM_BYTES <= 232448, "shared memory budget");

constexpr int BAR_G1_FULL = 0, BAR_G1_FULLB = 5, BAR_BIAS = 10, BAR_G1_EMPTY = 11, BAR_G1_DONE = 16, BAR_WA_DONE = 21,
              BAR_W2_EMPTY = 22, BAR_REM = 30, BAR_W2_FULL = 31, BAR_H_FULL = 39, BAR_H_EMPTY = 53, BAR_FLAG = 67,
              BAR_SENT = 73;
constexpr int NB_INIT = 1, NB_INIT2 = 2, NB_PUB = 3, NB_TAG = 9, NB_LAG = 11, NB_OUT = 12;

__host__ __device__ constexpr int h_slot(int s) {
    return s < 3 ? OFF_X + 2 * s * TILE : s == 3 ? OFF_SA : s == 4 ? OFF_W + 4 * TILE : OFF_X + (2 * s - 4) * TILE;
}
__host__ __device__ constexpr int slot_of(int u) { return u < 7 ? u % 5 : (u - 7) % 6 == 0 ? 5 : ((u - 7) % 6 + 1) % 5; }
__host__ __device__ constexpr int use_parity(int u) { return (u < 5 || u == 7 ? 0 : u < 7 ? 1 : (u - 7) % 6 == 0 ? (u - 7) / 6 : (u - 7) % 6 < 4 ? (u - 7) / 6 + 1 : (u - 7) / 6) & 1; }
__host__ __device__ constexpr bool reused(int u) { return u < 15; }

constexpr uint32_t T_K0 = 750;
constexpr uint32_t PACE = 460;
constexpr uint32_t T_PF5 = 3000;
constexpr uint32_t T_W2PF = 5300;
constexpr uint32_t T_REM = 1700;
constexpr uint32_t T_MB = 3500;
constexpr uint32_t T_REMCHK = 6900;
constexpr uint32_t ST_PACE_A = 120;
constexpr uint32_t ST_PACE_B = 175;
constexpr uint32_t ST_PACE_C = 215;
constexpr uint32_t POLL_DELAY = 400;
constexpr uint32_t REMSTEP = 400;
constexpr uint32_t SPIN_LIMIT = 1u << 20;

struct Scratch {
    uint4 h[SEQ * FF * 2 / 16];
    uint4 rem[8 * 24 * 2048 / 16];
    unsigned flag[32 * 32];
    unsigned started[32];
    unsigned epoch[NCTAS * 4];
};
__device__ Scratch g_scratch;

__device__ __forceinline__ void mbar_init(uint32_t bar, uint32_t cnt) {
    asm volatile("mbarrier.init.shared::cta.b64 [%0], %1;" ::"r"(bar), "r"(cnt) : "memory");
}
__device__ __forceinline__ void fence_mbar_init() { asm volatile("fence.mbarrier_init.release.cluster;" ::: "memory"); }
__device__ __forceinline__ void mbar_expect_tx(uint32_t bar, uint32_t bytes) {
    asm volatile("mbarrier.arrive.expect_tx.shared::cta.b64 _, [%0], %1;" ::"r"(bar), "r"(bytes) : "memory");
}
__device__ __forceinline__ void mbar_arrive(uint32_t bar) {
    asm volatile("mbarrier.arrive.shared::cta.b64 _, [%0];" ::"r"(bar) : "memory");
}
__device__ __forceinline__ void mbar_wait(uint32_t bar, uint32_t parity) {
    asm volatile(
        "{\n .reg .pred P; .reg .u32 n;\n"
        " mbarrier.try_wait.parity.shared::cta.b64 P, [%0], %1;\n @P bra WAIT_DONE;\n mov.u32 n, 0;\n"
        "WAIT_LOOP:\n mbarrier.try_wait.parity.shared::cta.b64 P, [%0], %1;\n @P bra WAIT_DONE;\n"
        " add.u32 n, n, 1;\n setp.lt.u32 P, n, %2;\n @P bra WAIT_LOOP;\n trap;\n"
        "WAIT_DONE:\n }" ::"r"(bar), "r"(parity), "n"(SPIN_LIMIT) : "memory");
}
__device__ __forceinline__ uint32_t mbar_test(uint32_t bar, uint32_t parity) {
    uint32_t ok;
    asm volatile("{ .reg .pred P; mbarrier.test_wait.parity.shared::cta.b64 P, [%1], %2; selp.u32 %0, 1, 0, P; }"
                 : "=r"(ok) : "r"(bar), "r"(parity) : "memory");
    return ok;
}
__device__ __forceinline__ bool elect_one() {
    uint32_t p;
    asm volatile("{ .reg .pred P; elect.sync _|P, 0xffffffff; selp.u32 %0, 1, 0, P; }" : "=r"(p));
    return p;
}
__device__ __forceinline__ void tma_load(uint32_t dst, const CUtensorMap* m, int c0, int c1, uint32_t bar) {
    asm volatile("cp.async.bulk.tensor.2d.shared::cluster.global.mbarrier::complete_tx::bytes [%0], [%1, {%3, %4}], [%2];"
                 ::"r"(dst), "l"(m), "r"(bar), "r"(c0), "r"(c1) : "memory");
}
__device__ __forceinline__ void tma_store(const CUtensorMap* m, uint32_t src, int c0, int c1) {
    asm volatile("cp.async.bulk.tensor.2d.global.shared::cta.bulk_group [%0, {%2, %3}], [%1];"
                 ::"l"(m), "r"(src), "r"(c0), "r"(c1) : "memory");
}
__device__ __forceinline__ void bulk_load(uint32_t dst, const void* src, uint32_t bytes, uint32_t bar) {
    asm volatile("cp.async.bulk.shared::cluster.global.mbarrier::complete_tx::bytes [%0], [%1], %2, [%3];"
                 ::"r"(dst), "l"(src), "r"(bytes), "r"(bar) : "memory");
}
__device__ __forceinline__ void bulk_store(void* dst, uint32_t src, uint32_t bytes) {
    asm volatile("cp.async.bulk.global.shared::cta.bulk_group [%0], [%1], %2;" ::"l"(dst), "r"(src), "r"(bytes) : "memory");
}
__device__ __forceinline__ void bulk_commit() { asm volatile("cp.async.bulk.commit_group;" ::: "memory"); }
template <int N> __device__ __forceinline__ void bulk_wait() { asm volatile("cp.async.bulk.wait_group %0;" ::"n"(N) : "memory"); }
__device__ __forceinline__ void prefetch_line(const void* p) { asm volatile("prefetch.global.L2 [%0];" ::"l"(p)); }
__device__ __forceinline__ void prefetch_bulk(const void* p, uint32_t bytes) {
    asm volatile("cp.async.bulk.prefetch.L2.global [%0], %1;" ::"l"(p), "r"(bytes) : "memory");
}
__device__ __forceinline__ void prefetch_box(const CUtensorMap* m, int c0, int c1) {
    asm volatile("cp.async.bulk.prefetch.tensor.2d.L2.global [%0, {%1, %2}];" ::"l"(m), "r"(c0), "r"(c1) : "memory");
}
__device__ __forceinline__ void prefetch_map(const CUtensorMap* m) { asm volatile("prefetch.tensormap [%0];" ::"l"(m) : "memory"); }
__device__ __forceinline__ void named_sync(int id, int n) { asm volatile("bar.sync %0, %1;" ::"r"(id), "r"(n) : "memory"); }
__device__ __forceinline__ void named_arrive(int id, int n) { asm volatile("bar.arrive %0, %1;" ::"r"(id), "r"(n) : "memory"); }
__device__ __forceinline__ void wg_fence() { asm volatile("wgmma.fence.sync.aligned;" ::: "memory"); }
__device__ __forceinline__ void wg_commit() { asm volatile("wgmma.commit_group.sync.aligned;" ::: "memory"); }
template <int N> __device__ __forceinline__ void wg_wait() { asm volatile("wgmma.wait_group.sync.aligned %0;" ::"n"(N) : "memory"); }
__device__ __forceinline__ void fence_async_smem() { asm volatile("fence.proxy.async.shared::cta;" ::: "memory"); }
__device__ __forceinline__ unsigned ld_relaxed(const unsigned* p) {
    unsigned v;
    asm volatile("ld.relaxed.gpu.global.u32 %0, [%1];" : "=r"(v) : "l"(p) : "memory");
    return v;
}
__device__ __forceinline__ void st_relaxed(unsigned* p, unsigned v) {
    asm volatile("st.relaxed.gpu.global.u32 [%0], %1;" ::"l"(p), "r"(v) : "memory");
}
__device__ __forceinline__ uint32_t lds32(uint32_t addr) {
    uint32_t v;
    asm volatile("ld.shared.u32 %0, [%1];" : "=r"(v) : "r"(addr));
    return v;
}
__device__ __forceinline__ void sts128(uint32_t addr, uint4 v) {
    asm volatile("st.shared.v4.u32 [%0], {%1, %2, %3, %4};" ::"r"(addr), "r"(v.x), "r"(v.y), "r"(v.z), "r"(v.w) : "memory");
}
__device__ __forceinline__ void stmatrix4(uint32_t addr, uint32_t a, uint32_t b, uint32_t c, uint32_t d) {
    asm volatile("stmatrix.sync.aligned.m8n8.x4.shared.b16 [%0], {%1, %2, %3, %4};" ::"r"(addr), "r"(a), "r"(b), "r"(c), "r"(d) : "memory");
}
__device__ __forceinline__ uint32_t read_clock() {
    uint32_t c;
    asm volatile("mov.u32 %0, %clock;" : "=r"(c));
    return c;
}
__device__ __forceinline__ void wait_until(uint32_t t0, uint32_t dt) {
    while (read_clock() - t0 < dt) { }
}
__device__ __forceinline__ void idle_until(uint32_t t0, uint32_t dt) {
    while (read_clock() - t0 < dt) __nanosleep(20);
}
__device__ __forceinline__ uint32_t plus_one(uint32_t v) {
    uint32_t r;
    asm volatile("add.u32 %0, %1, 1;" : "=r"(r) : "r"(v));
    return r;
}
__device__ __forceinline__ uint32_t pack_bf16(float lo, float hi) {
    uint32_t r;
    asm("cvt.rn.bf16x2.f32 %0, %1, %2;" : "=r"(r) : "f"(hi), "f"(lo));
    return r;
}
__device__ __forceinline__ uint32_t fma_bf16(uint32_t a, uint32_t b, uint32_t c) {
    uint32_t r;
    asm("fma.rn.bf16x2 %0, %1, %2, %3;" : "=r"(r) : "r"(a), "r"(b), "r"(c));
    return r;
}
__device__ __forceinline__ uint32_t relu_sq_bf16(float lo, float hi) {
    uint32_t r;
    asm("{ .reg .b32 t; cvt.rn.relu.bf16x2.f32 t, %1, %2; mul.rn.bf16x2 %0, t, t; }" : "=r"(r) : "f"(hi), "f"(lo));
    return r;
}
__host__ __device__ constexpr uint32_t desc_hi(uint32_t sbo, uint32_t mode) { return (sbo >> 4) | (mode << 30); }
__device__ __forceinline__ uint32_t desc_lo(uint32_t addr, uint32_t lbo) { return ((addr & 0x3FFFF) >> 4) | ((lbo >> 4) << 16); }

template <uint32_t AHI, uint32_t BHI>
__device__ __forceinline__ void wgmma_ss_n128_lo(float (&d)[96], uint32_t da, uint32_t db, uint32_t acc) {
    asm volatile("{ .reg .pred p; .reg .b64 da, db; setp.ne.b32 p, %66, 0; mov.b64 da, {%64, %67}; mov.b64 db, {%65, %68};\n"
        "wgmma.mma_async.sync.aligned.m64n128k16.f32.bf16.bf16 {%0, %1, %2, %3, %4, %5, %6, %7, %8, %9, %10, %11, %12, %13, %14, %15, %16, %17, %18, %19, %20, %21, %22, %23, %24, %25, %26, %27, %28, %29, %30, %31, %32, %33, %34, %35, %36, %37, %38, %39, %40, %41, %42, %43, %44, %45, %46, %47, %48, %49, %50, %51, %52, %53, %54, %55, %56, %57, %58, %59, %60, %61, %62, %63}, da, db, p, 1, 1, 0, 1; }"
        : "+f"(d[0]), "+f"(d[1]), "+f"(d[2]), "+f"(d[3]), "+f"(d[4]), "+f"(d[5]), "+f"(d[6]), "+f"(d[7]), "+f"(d[8]), "+f"(d[9]), "+f"(d[10]), "+f"(d[11]), "+f"(d[12]), "+f"(d[13]), "+f"(d[14]), "+f"(d[15]), "+f"(d[16]), "+f"(d[17]), "+f"(d[18]), "+f"(d[19]), "+f"(d[20]), "+f"(d[21]), "+f"(d[22]), "+f"(d[23]), "+f"(d[24]), "+f"(d[25]), "+f"(d[26]), "+f"(d[27]), "+f"(d[28]), "+f"(d[29]), "+f"(d[30]), "+f"(d[31]), "+f"(d[32]), "+f"(d[33]), "+f"(d[34]), "+f"(d[35]), "+f"(d[36]), "+f"(d[37]), "+f"(d[38]), "+f"(d[39]), "+f"(d[40]), "+f"(d[41]), "+f"(d[42]), "+f"(d[43]), "+f"(d[44]), "+f"(d[45]), "+f"(d[46]), "+f"(d[47]), "+f"(d[48]), "+f"(d[49]), "+f"(d[50]), "+f"(d[51]), "+f"(d[52]), "+f"(d[53]), "+f"(d[54]), "+f"(d[55]), "+f"(d[56]), "+f"(d[57]), "+f"(d[58]), "+f"(d[59]), "+f"(d[60]), "+f"(d[61]), "+f"(d[62]), "+f"(d[63])
        : "r"(da), "r"(db), "r"(acc), "n"(AHI), "n"(BHI));
}
template <uint32_t AHI, uint32_t BHI>
__device__ __forceinline__ void wgmma_ss_n64_hi(float (&d)[96], uint32_t da, uint32_t db, uint32_t acc) {
    asm volatile("{ .reg .pred p; .reg .b64 da, db; setp.ne.b32 p, %34, 0; mov.b64 da, {%32, %35}; mov.b64 db, {%33, %36};\n"
        "wgmma.mma_async.sync.aligned.m64n64k16.f32.bf16.bf16 {%0, %1, %2, %3, %4, %5, %6, %7, %8, %9, %10, %11, %12, %13, %14, %15, %16, %17, %18, %19, %20, %21, %22, %23, %24, %25, %26, %27, %28, %29, %30, %31}, da, db, p, 1, 1, 0, 1; }"
        : "+f"(d[64]), "+f"(d[65]), "+f"(d[66]), "+f"(d[67]), "+f"(d[68]), "+f"(d[69]), "+f"(d[70]), "+f"(d[71]), "+f"(d[72]), "+f"(d[73]), "+f"(d[74]), "+f"(d[75]), "+f"(d[76]), "+f"(d[77]), "+f"(d[78]), "+f"(d[79]), "+f"(d[80]), "+f"(d[81]), "+f"(d[82]), "+f"(d[83]), "+f"(d[84]), "+f"(d[85]), "+f"(d[86]), "+f"(d[87]), "+f"(d[88]), "+f"(d[89]), "+f"(d[90]), "+f"(d[91]), "+f"(d[92]), "+f"(d[93]), "+f"(d[94]), "+f"(d[95])
        : "r"(da), "r"(db), "r"(acc), "n"(AHI), "n"(BHI));
}
template <uint32_t AHI, uint32_t BHI>
__device__ __forceinline__ void wgmma_ss_n80(float (&d)[40], uint32_t da, uint32_t db, uint32_t acc) {
    asm volatile("{ .reg .pred p; .reg .b64 da, db; setp.ne.b32 p, %42, 0; mov.b64 da, {%40, %43}; mov.b64 db, {%41, %44};\n"
        "wgmma.mma_async.sync.aligned.m64n80k16.f32.bf16.bf16 {%0, %1, %2, %3, %4, %5, %6, %7, %8, %9, %10, %11, %12, %13, %14, %15, %16, %17, %18, %19, %20, %21, %22, %23, %24, %25, %26, %27, %28, %29, %30, %31, %32, %33, %34, %35, %36, %37, %38, %39}, da, db, p, 1, 1, 0, 1; }"
        : "+f"(d[0]), "+f"(d[1]), "+f"(d[2]), "+f"(d[3]), "+f"(d[4]), "+f"(d[5]), "+f"(d[6]), "+f"(d[7]), "+f"(d[8]), "+f"(d[9]), "+f"(d[10]), "+f"(d[11]), "+f"(d[12]), "+f"(d[13]), "+f"(d[14]), "+f"(d[15]), "+f"(d[16]), "+f"(d[17]), "+f"(d[18]), "+f"(d[19]), "+f"(d[20]), "+f"(d[21]), "+f"(d[22]), "+f"(d[23]), "+f"(d[24]), "+f"(d[25]), "+f"(d[26]), "+f"(d[27]), "+f"(d[28]), "+f"(d[29]), "+f"(d[30]), "+f"(d[31]), "+f"(d[32]), "+f"(d[33]), "+f"(d[34]), "+f"(d[35]), "+f"(d[36]), "+f"(d[37]), "+f"(d[38]), "+f"(d[39])
        : "r"(da), "r"(db), "r"(acc), "n"(AHI), "n"(BHI));
}
template <uint32_t BHI>
__device__ __forceinline__ void wgmma_rs_n80(float (&d)[40], uint32_t a0, uint32_t a1, uint32_t a2, uint32_t a3, uint32_t db, uint32_t acc) {
    asm volatile("{ .reg .pred p; .reg .b64 db; setp.ne.b32 p, %45, 0; mov.b64 db, {%44, %46};\n"
        "wgmma.mma_async.sync.aligned.m64n80k16.f32.bf16.bf16 {%0, %1, %2, %3, %4, %5, %6, %7, %8, %9, %10, %11, %12, %13, %14, %15, %16, %17, %18, %19, %20, %21, %22, %23, %24, %25, %26, %27, %28, %29, %30, %31, %32, %33, %34, %35, %36, %37, %38, %39}, {%40, %41, %42, %43}, db, p, 1, 1, 1; }"
        : "+f"(d[0]), "+f"(d[1]), "+f"(d[2]), "+f"(d[3]), "+f"(d[4]), "+f"(d[5]), "+f"(d[6]), "+f"(d[7]), "+f"(d[8]), "+f"(d[9]), "+f"(d[10]), "+f"(d[11]), "+f"(d[12]), "+f"(d[13]), "+f"(d[14]), "+f"(d[15]), "+f"(d[16]), "+f"(d[17]), "+f"(d[18]), "+f"(d[19]), "+f"(d[20]), "+f"(d[21]), "+f"(d[22]), "+f"(d[23]), "+f"(d[24]), "+f"(d[25]), "+f"(d[26]), "+f"(d[27]), "+f"(d[28]), "+f"(d[29]), "+f"(d[30]), "+f"(d[31]), "+f"(d[32]), "+f"(d[33]), "+f"(d[34]), "+f"(d[35]), "+f"(d[36]), "+f"(d[37]), "+f"(d[38]), "+f"(d[39])
        : "r"(a0), "r"(a1), "r"(a2), "r"(a3), "r"(db), "r"(acc), "n"(BHI));
}

template <int LO, int HI, int N>
__device__ __forceinline__ void pin(float (&acc)[N]) {
#pragma unroll
    for (int i = LO; i < HI; i++) asm volatile("" : "+f"(acc[i])::"memory");
}

__device__ __forceinline__ int remote_slice(int i, int bj) {
    const int q = bj & 4;
    if (i < 4) return (q ^ 4) + i;
    const int r = q + i - 4;
    return r < bj ? r : r + 1;
}

__device__ __forceinline__ void load_g1_step(uint32_t sbase, const CUtensorMap* mx, const CUtensorMap* mw, int bi, int bj, int k, int s) {
    const uint32_t bar = sbase + OFF_BAR + 8 * (BAR_G1_FULL + s), barb = sbase + OFF_BAR + 8 * (BAR_G1_FULLB + s);
    mbar_expect_tx(bar, 3 * TILE);
    tma_load(sbase + OFF_W + 2 * W_ARR + s * TILE, mw, bj * 192 + 128, k * 64, bar);
    tma_load(sbase + OFF_X + s * 2 * TILE, mx, k * 64, bi * 128, bar);
    mbar_expect_tx(barb, 2 * TILE);
    tma_load(sbase + OFF_W + s * TILE, mw, bj * 192, k * 64, barb);
    tma_load(sbase + OFF_W + W_ARR + s * TILE, mw, bj * 192 + 64, k * 64, barb);
}

template <int M0>
__device__ __forceinline__ void activate(float (&acc)[96], uint32_t (&h)[48], uint32_t tag, uint32_t tile) {
    pin<8 * M0, 8 * M0 + 32>(acc);
#pragma unroll
    for (int m = M0; m < M0 + 4; m++) {
#pragma unroll
        for (int e = 0; e < 4; e++) h[4 * m + e] = relu_sq_bf16(acc[8 * m + 2 * e], acc[8 * m + 2 * e + 1]) | tag;
        stmatrix4(tile + (m & 3) * 2048, h[4 * m], h[4 * m + 1], h[4 * m + 2], h[4 * m + 3]);
    }
}

__device__ __noinline__ void repair_tile(uint32_t probe, const uint8_t* src, uint32_t tag) {
    bool patched = false;
#pragma unroll 1
    for (int m = 0; m < 2; m++) {
        if ((lds32(probe + m * 4096) ^ tag) & 0x8000u) {
            uint4 a, b;
            uint32_t n = 0;
            do {
                asm volatile("ld.relaxed.gpu.global.v4.u32 {%0, %1, %2, %3}, [%4];" : "=r"(a.x), "=r"(a.y), "=r"(a.z), "=r"(a.w) : "l"(src + m * 4096) : "memory");
                asm volatile("ld.relaxed.gpu.global.v4.u32 {%0, %1, %2, %3}, [%4];" : "=r"(b.x), "=r"(b.y), "=r"(b.z), "=r"(b.w) : "l"(src + m * 4096 + 16) : "memory");
                if (++n > SPIN_LIMIT) __trap();
            } while (((a.x ^ tag) | (a.y ^ tag) | (a.z ^ tag) | (a.w ^ tag) | (b.x ^ tag) | (b.y ^ tag) | (b.z ^ tag) | (b.w ^ tag)) & 0x80008000u);
            sts128((probe & ~31u) + m * 4096, a);
            sts128((probe & ~31u) + m * 4096 + 16, b);
            patched = true;
        }
    }
    if (patched) fence_async_smem();
    __syncwarp();
}

template <bool BY_SM>
__global__ void __launch_bounds__(NTHREADS, 1)
mlp_kernel(const __grid_constant__ CUtensorMap map_x, const __grid_constant__ CUtensorMap map_w1,
           const __grid_constant__ CUtensorMap map_w2, const __grid_constant__ CUtensorMap map_out,
           const __grid_constant__ CUtensorMap map_out2,
           const uint8_t* __restrict__ x, const uint8_t* __restrict__ w1, const uint8_t* __restrict__ b1,
           const uint8_t* __restrict__ w2, const uint8_t* __restrict__ b2, Scratch* scr
) {
    const uint32_t t_entry = read_clock();
    extern __shared__ __align__(1024) uint8_t smem_raw[];
    uint32_t sbase = (uint32_t)__cvta_generic_to_shared(smem_raw);
    asm volatile("mov.u32 %0, %0;" : "+r"(sbase));
    sbase = __shfl_sync(0xffffffff, sbase, 0);
    const uint32_t bars = sbase + OFF_BAR;
    const int warp = __shfl_sync(0xffffffff, threadIdx.x >> 5, 0);
    const int lane = threadIdx.x & 31;

    uint32_t id = blockIdx.x;
    if (BY_SM) asm volatile("mov.u32 %0, %smid;" : "=r"(id));
    if (threadIdx.x < 32 && id < 128) {
        const uint8_t* a = threadIdx.x < 16 ? x + (id * 16 + threadIdx.x) * (DM * 2)
                           : threadIdx.x < 28 ? w1 + id * 1536 + (threadIdx.x - 16) * 128 : b1 + (id & 7) * 384 + (threadIdx.x - 28) * 128;
        if (threadIdx.x < 28 || (threadIdx.x < 31 && id < 8)) prefetch_line(a);
    }
    const int p = id >> 1;
    if (p == 60 || p == 61) {
        if (threadIdx.x == 0) {
            unsigned* const my_epoch = scr->epoch + 512 + (id - 120);
            const unsigned epoch = ld_relaxed(my_epoch) + 1;
            asm volatile("red.relaxed.gpu.global.add.u32 [%0], 1;" ::"l"(scr->started) : "memory");
            idle_until(t_entry, 9000);
            for (uint32_t n = 0; ld_relaxed(scr->started) != epoch * NCTAS; n++)
                if (n > SPIN_LIMIT) __trap();
            *my_epoch = epoch;
        }
        return;
    }
    const int q7 = ((p - 32) * 37) >> 8;
    const int slot = p < 32 ? p >> 3 : p < 60 ? 4 + q7 : p - 58;
    const int g = p < 32 ? p & 7 : p < 60 ? p - 31 - 7 * q7 : 0;
    const int cta = (g * 8 + slot) * 2 + (id & 1);
    const int bi = (g >> 1) * 4 + (slot >> 1);
    const int bj = (g & 1) * 4 + (slot & 1) * 2 + (id & 1);

    if (warp == 8) {
        if (elect_one()) {
            mbar_init(bars + 8 * BAR_G1_FULL, 1);
            fence_mbar_init();
            mbar_expect_tx(bars + 8 * BAR_G1_FULL, 3 * TILE);
            tma_load(sbase + OFF_X, &map_x, 0, bi * 128, bars + 8 * BAR_G1_FULL);
            tma_load(sbase + OFF_W + 2 * W_ARR, &map_w1, bj * 192 + 128, 0, bars + 8 * BAR_G1_FULL);
            mbar_init(bars + 8 * (BAR_G1_FULL + 1), 1);
            mbar_init(bars + 8 * (BAR_G1_FULLB + 1), 1);
            fence_mbar_init();
        }
        named_arrive(NB_INIT, NTHREADS);
        unsigned* const my_flag = scr->flag + bi * 64 + bj;
        unsigned prev0 = 0, prev1 = 0;
#pragma unroll
        for (int k = 1; k < 5; k++) {
            if (k == 2) {
                named_sync(NB_INIT2, 64);
                prev0 = ld_relaxed(my_flag);
                prev1 = ld_relaxed(my_flag + 32);
            }
            wait_until(t_entry, T_K0 + k * PACE);
            if (elect_one()) {
                load_g1_step(sbase, &map_x, &map_w1, bi, bj, k, k);
            }
        }
        const unsigned epoch0 = plus_one(prev0), epoch1 = plus_one(prev1);
#pragma unroll 1
        for (int k = 5; k < 10; k++) {
            mbar_wait(bars + 8 * (BAR_G1_EMPTY + k - 5), 0);
            if (elect_one()) {
                load_g1_step(sbase, &map_x, &map_w1, bi, bj, k, k - 5);
            }
        }
        uint8_t* const hdst = reinterpret_cast<uint8_t*>(scr->h) + (size_t)(bi * 24 + bj * 3) * 2 * TILE;
#pragma unroll 1
        for (int e = 0; e < 6; e++) {
            const int r = e >> 1, w = e & 1;
            named_sync(NB_PUB + e, 160);
            fence_async_smem();
            const uint32_t tp = read_clock();
            uint8_t* const dst = hdst + ((r == 0 ? 2 : r - 1) * 2 + w) * TILE;
            const uint32_t src = sbase + (r == 0 ? OFF_SA : OFF_X + (2 + r) * 2 * TILE) + w * TILE;
            const uint32_t pace = r == 0 ? ST_PACE_A : r == 1 ? ST_PACE_B : ST_PACE_C;
            if (elect_one()) {
#pragma unroll 1
                for (int q = 0; q < 4; q++) {
                    wait_until(tp, q * pace);
                    bulk_store(dst + q * 2048, src + q * 2048, 2048);
                }
                bulk_commit();
                st_relaxed(my_flag + w * 32 + r * 8, w ? epoch1 : epoch0);
                mbar_arrive(bars + 8 * (BAR_SENT + e));
                if (e != 0 && e != 2) {
                    bulk_wait<1>();
                    const int pr = (e - 1) >> 1;
                    mbar_arrive(bars + 8 * (BAR_H_EMPTY + (w ^ 1) * 7 + (pr == 0 ? 3 : 4 + pr)));
                }
                if (e == 1 || e == 5) {
                    bulk_wait<0>();
                    mbar_arrive(bars + 8 * (BAR_H_EMPTY + 7 + (r == 0 ? 3 : 6)));
                }
            }
            idle_until(tp, 4 * pace);
        }
        return;
    }

    if (warp == 13) {
        if (elect_one()) {
            mbar_init(bars + 8 * BAR_BIAS, 1);
            mbar_init(bars + 8 * BAR_G1_FULLB, 1);
            fence_mbar_init();
            mbar_expect_tx(bars + 8 * BAR_BIAS, 384);
#pragma unroll
            for (int a = 0; a < 3; a++) bulk_load(sbase + OFF_SA + a * 2048, b1 + bj * 384 + a * 128, 128, bars + 8 * BAR_BIAS);
            mbar_expect_tx(bars + 8 * BAR_G1_FULLB, 2 * TILE);
            tma_load(sbase + OFF_W, &map_w1, bj * 192, 0, bars + 8 * BAR_G1_FULLB);
            tma_load(sbase + OFF_W + W_ARR, &map_w1, bj * 192 + 64, 0, bars + 8 * BAR_G1_FULLB);
#pragma unroll
            for (int b = 2; b < 5; b++) {
                mbar_init(bars + 8 * (BAR_G1_FULL + b), 1);
                mbar_init(bars + 8 * (BAR_G1_FULLB + b), 1);
            }
            fence_mbar_init();
        }
    } else if (warp > 8) {
        if (elect_one()) {
            const uint32_t b0 = bars + 8 * (11 + (warp - 9) * 19);
#pragma unroll
            for (int b = 0; b < 19; b++) mbar_init(b0 + 8 * b, warp == 9 ? 2 : 1);
            fence_mbar_init();
        }
    } else {
        const uint32_t z = sbase + OFF_SA + threadIdx.x * 16;
        if (threadIdx.x & 0x78) sts128(z, make_uint4(0, 0, 0, 0));
        if (threadIdx.x >= 8 && threadIdx.x < 144) sts128(z + 4096, make_uint4((threadIdx.x & 0xf8) == 128 ? 0x3f80u : 0u, 0, 0, 0));
        fence_async_smem();
    }
    named_sync(NB_INIT, NTHREADS);

    if (warp > 8) {
        if (warp == 9) {
            named_arrive(NB_INIT2, 64);
            idle_until(t_entry, 2500);
            if (elect_one()) {
                prefetch_map(&map_w2);
                prefetch_map(&map_out);
                prefetch_map(&map_out2);
            }
            int crow[7];
#pragma unroll
            for (int i = 0; i < 7; i++) crow[i] = remote_slice(i, bj) * 192;
#pragma unroll
            for (int t = 0; t < 24; t++) {
                const int q = t % W2_SLOTS;
                if (t >= W2_SLOTS) mbar_wait(bars + 8 * (BAR_W2_EMPTY + q), (t / W2_SLOTS - 1) & 1);
                else if ((t & 1) == 0) mbar_wait(bars + 8 * (BAR_G1_DONE + (t >> 1)), 0);
                const int row = t < 3 ? bj * 192 + ((t + 2) % 3) * 64 : crow[(t - 3) % 7] + (((t - 3) / 7 + 2) % 3) * 64;
                if (elect_one()) {
                    mbar_expect_tx(bars + 8 * (BAR_W2_FULL + q), TILE);
                    tma_load(sbase + OFF_W + (q & 1) * W_ARR + (q >> 1) * TILE, &map_w2, bj * 64, row, bars + 8 * (BAR_W2_FULL + q));
                }
            }
        } else if (warp & 1) {
            const int hw = warp == 13;
            unsigned* const my_epoch = scr->epoch + cta * 4 + 1 + hw;
            const unsigned epoch = ld_relaxed(my_epoch) + 1;
            if (hw == 0) {
                idle_until(t_entry, 2500);
                uint4 bv;
                if (lane < 10) bv = __ldg(reinterpret_cast<const uint4*>(b2 + (lane < 8 ? bj * 128 + lane * 16 : 1024 + bj * 32 + (lane - 8) * 16)));
#pragma unroll 1
                for (int k = 5; k < 10; k++) {
                    idle_until(t_entry, T_PF5 + (k - 5) * PACE);
                    if (elect_one()) {
                        prefetch_bulk(w1 + (size_t)k * 64 * (FF * 2) + cta * 1536, 1536);
                        if (bj == k - 5) prefetch_box(&map_x, k * 64, bi * 128);
                    }
                }
                if (lane < 10) sts128(sbase + OFF_BIAS + 384 + lane * 16, bv);
                if (lane == 10) sts128(sbase + OFF_BIAS + 544, make_uint4((epoch & 1) ? 0x80008000u : 0u, 0, 0, 0));
                named_arrive(NB_TAG, 160);
                named_arrive(NB_TAG + 1, 160);
                idle_until(t_entry, T_W2PF + (cta & 3) * 350);
                if (elect_one()) prefetch_bulk(w2 + (size_t)cta * 12 * (DM * 2), 12 * DM * 2);
            }
            if (lane == 0) *my_epoch = epoch;
#pragma unroll 1
            for (int e = hw; e < 6; e += 2) {
                const unsigned* probe = scr->flag + bi * 64 + hw * 32 + (e >> 1) * 8 + (lane & 7);
                mbar_wait(bars + 8 * (BAR_SENT + e), 0);
                idle_until(read_clock(), POLL_DELAY);
                for (uint32_t n = 0; !__all_sync(0xffffffff, ld_relaxed(probe) == epoch); n++)
                    if (n > SPIN_LIMIT) __trap();
                if (lane == 0) { mbar_arrive(bars + 8 * (BAR_FLAG + e)); }
            }
        } else {
            const int hw = warp == 12;
            if (hw == 0) {
                unsigned* const my_epoch = scr->epoch + cta * 4;
                const unsigned prev = ld_relaxed(my_epoch);
                idle_until(t_entry, T_REM);
                const int t = (lane >> 1) & 3, e = lane & 1, jl = lane >> 3;
                uint4 v[6];
#pragma unroll
                for (int m = 0; m < 6; m++) {
                    const int pr = cta * 3 + (m >> 1), c = pr >> 4, r = pr & 15;
                    v[m] = __ldg(reinterpret_cast<const uint4*>(w2 + (size_t)(c * 64 + t * 16 + r) * (DM * 2) + 1024 + ((m & 1) * 4 + jl) * 32 + e * 16));
                }
#pragma unroll
                for (int m = 0; m < 6; m++) {
                    const int pr = cta * 3 + (m >> 1), c = pr >> 4, r = pr & 15;
                    scr->rem[(((m & 1) * 4 + jl) * 24 + c) * 128 + r * 8 + ((lane & 7) ^ (r & 7))] = v[m];
                }
                __syncwarp();
                idle_until(t_entry, T_MB);
                if (lane == 0) asm volatile("red.release.gpu.global.add.u32 [%0], 1;" ::"l"(scr->started) : "memory");
                idle_until(t_entry, T_REMCHK);
                for (uint32_t n = 0; ld_relaxed(scr->started) != (prev + 1) * NCTAS; n++) {
                    if (n > SPIN_LIMIT) __trap();
                    idle_until(read_clock(), 400);
                }
                asm volatile("fence.acquire.gpu;\n fence.proxy.async.global;" ::: "memory");
                if (lane == 0) { *my_epoch = prev + 1; }
                if (elect_one()) mbar_expect_tx(bars + 8 * BAR_REM, 6 * TILE);
                mbar_wait(bars + 8 * BAR_WA_DONE, 0);
                const uint32_t ta = read_clock();
#pragma unroll
                for (int r = 0; r < 3; r++) {
                    idle_until(ta, r * REMSTEP);
                    if (elect_one()) {
                        bulk_load(sbase + OFF_REM + r * 2 * TILE, reinterpret_cast<const uint8_t*>(scr->rem) + (bj * 3 + r) * 2 * TILE, 2 * TILE, bars + 8 * BAR_REM);
                    }
                }
            }
            const uint8_t* himg = reinterpret_cast<const uint8_t*>(scr->h) + (size_t)(bi * 48 + hw) * TILE;
            uint32_t hoff[7];
#pragma unroll
            for (int i = 0; i < 7; i++) hoff[i] = remote_slice(i, bj) * 6 * TILE;
            const uint32_t hb = bars + hw * 56, ring = sbase + hw * TILE, ring4 = sbase + hw * W_ARR;
#pragma unroll
            for (int u = 0; u < 21; u++) {
                const int r = u / 7, i = u % 7, s = slot_of(u);
                if (i == 0) mbar_wait(bars + 8 * (BAR_FLAG + 2 * r) + 8 * hw, 0);
                if (u == 4) mbar_wait(bars + 8 * (BAR_G1_DONE + 4), 0);
                mbar_wait(hb + 8 * (BAR_H_EMPTY + s), use_parity(u));
                const uint32_t fb = hb + 8 * (BAR_H_FULL + s);
                if (elect_one()) {
                    mbar_expect_tx(fb, TILE);
                    bulk_load((s == 4 ? ring4 : ring) + h_slot(s), himg + hoff[i] + ((r + 2) % 3) * 2 * TILE, TILE, fb);
                }
            }
        }
        return;
    }

    const int wg = warp >> 2;
    const bool signaler = (threadIdx.x & 127) == 0;
    const uint32_t bias_s = sbase + OFF_BIAS + (lane & 3) * 4;
    constexpr uint32_t HI_SW = desc_hi(1024, 1), HI_H = desc_hi(128, 0);
    const uint32_t xhalf = sbase + OFF_X + wg * TILE;
    const uint32_t hempty = bars + 8 * BAR_H_EMPTY + wg * 56, hfull = bars + 8 * BAR_H_FULL + wg * 56;
    const uint32_t stg = ((lane >> 4) * 8 + (warp & 3) * 2 + ((lane >> 3) & 1)) * 128 + (lane & 7) * 16 + sbase + wg * TILE;
    float acc1[96];
    uint32_t hreg[48], tag;

    {
        const uint32_t dbias = desc_lo(sbase + OFF_SA, 2048), dones = desc_lo(sbase + OFF_SA + 6144, 128);
        mbar_wait(bars + 8 * BAR_BIAS, 0);
        wg_fence();
        wgmma_ss_n64_hi<desc_hi(0, 0), HI_SW>(acc1, dones, dbias + (4096 >> 4), 0);
        wgmma_ss_n128_lo<desc_hi(0, 0), HI_SW>(acc1, dones, dbias, 0);
        wg_commit();
    }
    const uint32_t dx0 = desc_lo(xhalf, 16), dw0 = desc_lo(sbase + OFF_W, W_ARR);
    mbar_wait(bars + 8 * BAR_G1_FULL, 0);
#pragma unroll
    for (int n = 0; n < 15; n++) {
        const int s = n % 5;
        const uint32_t da = dx0 + s * (2 * TILE >> 4), db = dw0 + s * (TILE >> 4);
        const uint32_t nbar = bars + 8 * (BAR_G1_FULL + (n + 1) % 5), nbarb = bars + 8 * (BAR_G1_FULLB + (n + 1) % 5), npar = n >= 4;
        const bool needa = n < 9, needb = n < 4 || (n >= 9 && n < 14);
        uint32_t ok = 1;
        wg_fence();
        if (n == 0) {
#pragma unroll
            for (int kk = 0; kk < 4; kk++) wgmma_ss_n64_hi<HI_SW, HI_SW>(acc1, da + kk * 2, db + (2 * W_ARR >> 4) + kk * 128, 1);
            wg_commit();
            mbar_wait(bars + 8 * BAR_G1_FULLB, 0);
            wg_fence();
        }
#pragma unroll
        for (int kk = 0; kk < 4; kk++) {
            if (n > 0 && n < 10) wgmma_ss_n64_hi<HI_SW, HI_SW>(acc1, da + kk * 2, db + (2 * W_ARR >> 4) + kk * 128, 1);
            if (n < 5 || n >= 10) wgmma_ss_n128_lo<HI_SW, HI_SW>(acc1, da + kk * 2, db + kk * 128, 1);
            if (kk == (n < 5 ? 0 : 1) && ((n >= 1 && n <= 5) || n >= 10)) {
                wg_commit();
                wg_wait<1>();
                if (signaler) {
                    mbar_arrive(bars + 8 * (n <= 5 ? BAR_G1_EMPTY + n - 1 : n == 10 ? BAR_WA_DONE : BAR_G1_DONE + n - 11));
                    if (n >= 11 && n <= 13) mbar_arrive(hempty + 8 * (n - 11));
                }
                if (n == 10) {
                    activate<8>(acc1, hreg, tag, stg + OFF_SA);
                    named_arrive(NB_PUB + wg, 160);
                }
                wg_fence();
            }
            if (kk == 2 && needa) ok &= mbar_test(nbar, npar);
            if (kk == 2 && needb) ok &= mbar_test(nbarb, npar);
            if (n == 9 && kk == 0) tag = lds32(sbase + OFF_BIAS + 544);
        }
        wg_commit();
        if (n == 7) named_sync(NB_TAG + wg, 160);
        if (n == 14 && wg == 0) named_arrive(NB_LAG, 256);
        if (n == 12 && wg == 1) named_sync(NB_LAG, 256);
        if (!ok) {
            if (needa) mbar_wait(nbar, npar);
            if (needb) mbar_wait(nbarb, npar);
        }
    }

    float acc2[40];
    uint32_t bias2[10];
    constexpr uint32_t DW2_KSTEP = 128u - (((2048u - 32u) >> 4) << 16), DW2_CHUNK = (2048u >> 4) << 16;
    const uint32_t db0 = desc_lo(sbase + OFF_W, OFF_REM - OFF_W), da0 = desc_lo(xhalf, 1024);
    const uint32_t half4 = wg * (W_ARR - TILE), da4 = da0 + (half4 >> 4);
    uint32_t dbs[8];
#pragma unroll
    for (int i = 0; i < 8; i++) dbs[i] = db0 + (i < 7 ? remote_slice(i, bj) : bj) * 3 * DW2_CHUNK;
    const uint32_t probe_off = (lane >> 3) * 1024 + (warp & 3) * 256 + (lane & 7) * 32;
    const uint32_t probe = xhalf + probe_off + (lane >> 2) * 4;
    const uint8_t* hsrc = reinterpret_cast<const uint8_t*>(scr->h) + (size_t)bi * 48 * TILE + wg * TILE + probe_off;
    wg_wait<0>();
    if (signaler) {
        mbar_arrive(bars + 8 * (BAR_G1_DONE + 4));
        mbar_arrive(hempty + 8 * 4);
    }
    activate<0>(acc1, hreg, tag, stg + OFF_X + 6 * TILE);
    named_arrive(NB_PUB + 2 + wg, 160);
    const uint32_t own_ok = mbar_test(bars + 8 * BAR_REM, 0) & mbar_test(bars + 8 * BAR_W2_FULL, 0) &
                            mbar_test(bars + 8 * (BAR_W2_FULL + 1), 0) & mbar_test(bars + 8 * (BAR_W2_FULL + 2), 0);
    activate<4>(acc1, hreg, tag, stg + OFF_X + 8 * TILE);
    named_arrive(NB_PUB + 4 + wg, 160);
    if (!own_ok) {
        mbar_wait(bars + 8 * BAR_REM, 0);
#pragma unroll 1
        for (int t = 0; t < 3; t++) mbar_wait(bars + 8 * (BAR_W2_FULL + t), 0);
    }
#pragma unroll
    for (int t = 0; t < 24; t++) {
        const bool own = t < 3, check = t >= 2 && t < 23;
        const int u = own ? 0 : t - 3, nu = check ? t - 2 : 0;
        const int c = own ? (t + 2) % 3 : (u / 7 + 2) % 3;
        const uint32_t woff = (((t % W2_SLOTS) & 1) * W_ARR + ((t % W2_SLOTS) >> 1) * TILE) >> 4;
        const uint32_t db = dbs[own ? 7 : u % 7] + c * DW2_CHUNK + woff - (woff << 16);
        const uint32_t da = (slot_of(u) == 4 ? da4 : da0) + (h_slot(slot_of(u)) >> 4);
        const uint32_t wbar = bars + 8 * (BAR_W2_FULL + (t + 1) % W2_SLOTS), wpar = ((t + 1) / W2_SLOTS) & 1;
        const uint32_t hbar = hfull + 8 * slot_of(nu), hpar = use_parity(nu);
        const uint32_t nprobe = probe + h_slot(slot_of(nu)) + (slot_of(nu) == 4 ? half4 : 0);
        const bool relw = t > 0 && t - 1 < 24 - W2_SLOTS, relh = t >= 4 && reused(t - 4);
        uint32_t ok = 1, stale = 0;
        bool slow = false;
        if (t == 12) {
#pragma unroll
            for (int jb = 0; jb < 10; jb++) bias2[jb] = lds32(bias_s + 384 + jb * 16);
        }
        if (t == 18) mbar_wait(hempty + 8 * 6, 0);
        wg_fence();
#pragma unroll
        for (int kk = 0; kk < 4; kk++) {
            const int f = own ? (c * 4 + kk) * 4 : 0;
            if (own) wgmma_rs_n80<HI_SW>(acc2, hreg[f], hreg[f + 1], hreg[f + 2], hreg[f + 3], db + kk * DW2_KSTEP, t | kk);
            else wgmma_ss_n80<HI_H, HI_SW>(acc2, da + kk * 128, db + kk * DW2_KSTEP, 1);
            if (kk == 1 && (relw || relh)) {
                wg_commit();
                wg_wait<1>();
                if (signaler) {
                    if (relh) mbar_arrive(hempty + 8 * slot_of(t >= 4 ? t - 4 : 0));
                    if (relw) mbar_arrive(bars + 8 * (BAR_W2_EMPTY + (t - 1) % W2_SLOTS));
                }
                wg_fence();
            }
            if (check && kk == 1) ok = mbar_test(wbar, wpar) & mbar_test(hbar, hpar);
            if (check && kk == 2) stale = (lds32(nprobe) ^ tag) | (lds32(nprobe + 4096) ^ tag);
            if (check && kk == 3) slow = __any_sync(0xffffffff, !ok || (stale & 0x8000u));
        }
        wg_commit();
        if (slow) {
            mbar_wait(wbar, wpar);
            mbar_wait(hbar, hpar);
            stale = (lds32(nprobe) ^ tag) | (lds32(nprobe + 4096) ^ tag);
            if (__any_sync(0xffffffff, stale & 0x8000u))
                repair_tile(nprobe, hsrc + (remote_slice(nu % 7, bj) * 3 + (nu / 7 + 2) % 3) * 2 * TILE, tag);
        }
    }
    wg_wait<0>();
    pin<0, 40>(acc2);

    const uint32_t sgn = 0x3f803f80u | tag;
    const int orow = (warp & 3) * 16 + (lane & 15);
    const uint32_t ost = xhalf + h_slot(6), ost2 = xhalf + h_slot(3);
#pragma unroll
    for (int m = 0; m < 5; m++) {
        uint32_t o[4];
#pragma unroll
        for (int e = 0; e < 4; e++) o[e] = fma_bf16(pack_bf16(acc2[8 * m + 2 * e], acc2[8 * m + 2 * e + 1]), sgn, bias2[2 * m + (e >> 1)]);
        stmatrix4(m < 4 ? ost + orow * 128 + (((2 * m + (lane >> 4)) ^ (lane & 7)) << 4) : ost2 + orow * 32 + (lane >> 4) * 16,
                  o[0], o[1], o[2], o[3]);
    }
    named_sync(NB_OUT + wg, 128);
    if ((warp & 3) == 0 && elect_one()) {
        fence_async_smem();
        tma_store(&map_out, ost, bj * 64, bi * 128 + wg * 64);
        tma_store(&map_out2, ost2, 512 + bj * 16, bi * 128 + wg * 64);
        asm volatile("cp.async.bulk.commit_group;\n cp.async.bulk.wait_group.read 0;" ::: "memory");
    }
}

__global__ void fallback_hidden(const __nv_bfloat16* x, const __nv_bfloat16* w1, const __nv_bfloat16* b1, __nv_bfloat16* h) {
    const int f = blockIdx.x * blockDim.x + threadIdx.x, s = blockIdx.y;
    float a = __bfloat162float(b1[f]);
    for (int d = 0; d < DM; d++) a += __bfloat162float(x[s * DM + d]) * __bfloat162float(w1[d * FF + f]);
    const float r = fmaxf(__bfloat162float(__float2bfloat16(a)), 0.f);
    h[s * FF + f] = __float2bfloat16(r * r);
}
__global__ void fallback_output(const __nv_bfloat16* h, const __nv_bfloat16* w2, const __nv_bfloat16* b2, __nv_bfloat16* out) {
    const int d = blockIdx.x * blockDim.x + threadIdx.x, s = blockIdx.y;
    float a = 0.f;
    for (int f = 0; f < FF; f++) a += __bfloat162float(h[s * FF + f]) * __bfloat162float(w2[f * DM + d]);
    out[s * DM + d] = __float2bfloat16(__bfloat162float(__float2bfloat16(a)) + __bfloat162float(b2[d]));
}

typedef CUresult (*EncodeTiledFn)(CUtensorMap*, CUtensorMapDataType, cuuint32_t, void*, const cuuint64_t*, const cuuint64_t*,
                                  const cuuint32_t*, const cuuint32_t*, CUtensorMapInterleave, CUtensorMapSwizzle,
                                  CUtensorMapL2promotion, CUtensorMapFloatOOBfill);

CUtensorMap make_map(EncodeTiledFn encode, void* base, int cols, int rows, int box_cols, int box_rows, bool swizzle) {
    CUtensorMap m;
    cuuint64_t dims[2] = {(cuuint64_t)cols, (cuuint64_t)rows}, strides[1] = {(cuuint64_t)cols * 2};
    cuuint32_t box[2] = {(cuuint32_t)box_cols, (cuuint32_t)box_rows}, es[2] = {1, 1};
    encode(&m, CU_TENSOR_MAP_DATA_TYPE_BFLOAT16, 2, base, dims, strides, box, es, CU_TENSOR_MAP_INTERLEAVE_NONE,
           swizzle ? CU_TENSOR_MAP_SWIZZLE_128B : CU_TENSOR_MAP_SWIZZLE_NONE, CU_TENSOR_MAP_L2_PROMOTION_L2_128B,
           CU_TENSOR_MAP_FLOAT_OOB_FILL_NONE);
    return m;
}

}

extern "C" void kernel_launch(void* const* d_in, const int* in_sizes, int n_in, void* d_out, int out_size) {
    void* scr = nullptr;
    cudaGetSymbolAddress(&scr, g_scratch);
    int dev = 0, sms = 0;
    cudaGetDevice(&dev);
    cudaDeviceGetAttribute(&sms, cudaDevAttrMultiProcessorCount, dev);
    if (sms < NCTAS) {
        __nv_bfloat16* h = reinterpret_cast<__nv_bfloat16*>(scr);
        fallback_hidden<<<dim3(FF / 256, SEQ), 256, 0, cudaStreamPerThread>>>((const __nv_bfloat16*)d_in[0], (const __nv_bfloat16*)d_in[1],
                                                                             (const __nv_bfloat16*)d_in[2], h);
        fallback_output<<<dim3(DM / 128, SEQ), 128, 0, cudaStreamPerThread>>>(h, (const __nv_bfloat16*)d_in[3], (const __nv_bfloat16*)d_in[4],
                                                                             (__nv_bfloat16*)d_out);
        return;
    }

    void* fn = nullptr;
    cudaDriverEntryPointQueryResult st;
    cudaGetDriverEntryPoint("cuTensorMapEncodeTiled", &fn, cudaEnableDefault, &st);
    EncodeTiledFn encode = (EncodeTiledFn)fn;
    const CUtensorMap map_x = make_map(encode, d_in[0], DM, SEQ, 64, 128, true);
    const CUtensorMap map_w1 = make_map(encode, d_in[1], FF, DM, 64, 64, true);
    const CUtensorMap map_w2 = make_map(encode, d_in[3], DM, FF, 64, 64, true);
    const CUtensorMap map_out = make_map(encode, d_out, DM, SEQ, 64, 64, true);
    const CUtensorMap map_out2 = make_map(encode, d_out, DM, SEQ, 16, 64, false);

    auto kernel = sms == NCTAS ? mlp_kernel<true> : mlp_kernel<false>;
    cudaFuncSetAttribute(kernel, cudaFuncAttributeMaxDynamicSharedMemorySize, SMEM_BYTES);
    kernel<<<NCTAS, NTHREADS, SMEM_BYTES, cudaStreamPerThread>>>(map_x, map_w1, map_w2, map_out, map_out2, (const uint8_t*)d_in[0],
        (const uint8_t*)d_in[1], (const uint8_t*)d_in[2], (const uint8_t*)d_in[3], (const uint8_t*)d_in[4], (Scratch*)scr);
}
```
